```python
import torch

def _softmax(x, axis=-1):
    return torch.softmax(x, dim=axis)
def _gelu(x):
    return torch.nn.functional.gelu(x, approximate="tanh")
def _silu(x):
    return torch.nn.functional.silu(x)
def _sigmoid(x):
    return torch.sigmoid(x)
def _layernorm(x, axis=-1, eps=1e-5):
    m = x.mean(dim=axis, keepdim=True)
    v = x.var(dim=axis, keepdim=True, unbiased=False)
    return (x - m) / torch.sqrt(v + eps)
def _scatter_add(tgt, idx, src, axis=0):
    return tgt.clone().index_add_(axis, idx, src)
def _segment_sum(src, seg, n):
    out = torch.zeros((n,) + src.shape[1:], dtype=src.dtype)
    return out.index_add_(0, seg, src)
def _pad(x, pw):
    flat = tuple(v for pair in reversed(pw) for v in pair)
    return torch.nn.functional.pad(x, flat)

kernel_name = 'sequential_preLN__softmax_full_mha__mixer_token_mlp__prompt'

def setup_inputs():

    _w = (lambda a: (lambda t: t.to(torch.bfloat16) if t.is_floating_point() else t)(torch.as_tensor(a)))
    def _A_setup():
        B, S, D = 1, 2048, 640
        return {
            "x": _w((lambda *s: torch.randn(*s, dtype=torch.bfloat16) * 0.05)(B, S, D)),
            "wqkv": _w((lambda *s: torch.randn(*s, dtype=torch.bfloat16) * 0.05)(D, 3 * D)),
            "wo": _w((lambda *s: torch.randn(*s, dtype=torch.bfloat16) * 0.05)(D, D)),
        }
    _A_in = _A_setup()

    def _B_setup():
        B, S, D, F = 1, 2048, 640, 1728
        return {
            "x": _w((lambda *s: torch.randn(*s, dtype=torch.bfloat16) * 0.05)(B, S, D)),
            "w1": _w((lambda *s: torch.randn(*s, dtype=torch.bfloat16) * 1.6)(S, F) * (S ** -0.5)),
            "b1": _w((lambda *s: torch.randn(*s, dtype=torch.bfloat16) * 1.6)(F) * 0.02),
            "w2": _w((lambda *s: torch.randn(*s, dtype=torch.bfloat16) * 0.2)(F, S) * (F ** -0.5)),
            "b2": _w((lambda *s: torch.randn(*s, dtype=torch.bfloat16) * 0.2)(S) * 0.02),
        }
    _B_in = _B_setup()

    return {
        "A_x": _A_in["x"],
        "A_wqkv": _A_in["wqkv"],
        "A_wo": _A_in["wo"],
        "B_x": _B_in["x"],
        "B_w1": _B_in["w1"],
        "B_b1": _B_in["b1"],
        "B_w2": _B_in["w2"],
        "B_b2": _B_in["b2"],
    }

def reference(A_x, A_wqkv, A_wo, B_x, B_w1, B_b1, B_w2, B_b2):
    def _A_ref(x, wqkv, wo):
        B, S, D = x.shape
        H = 32; Dh = D // H
        qkv = (lambda x, *d: x.permute(*d))((x @ wqkv).reshape(B, S, 3, H, Dh), 2, 0, 3, 1, 4)
        q, k, v = qkv[0], qkv[1], qkv[2]
        scale = Dh ** -0.5
        scores = torch.einsum("bhqd,bhkd->bhqk", q, k) * scale
        p = _softmax(scores, axis=-1)
        o = torch.einsum("bhqk,bhkd->bhqd", p, v)
        return (lambda x, *d: x.permute(*d))(o, 0, 2, 1, 3).reshape(B, S, D) @ wo

    def _B_ref(x, w1, b1, w2, b2):
        B, S, D = x.shape
        h = _layernorm(x, axis=-1)
        u = torch.einsum("bsd,sf->bdf", h, w1) + b1
        u = _gelu(u)
        y = torch.einsum("bdf,fs->bds", u, w2) + b2
        return (lambda x, *d: x.permute(*d))(y, 0, 2, 1)

    x = A_x
    h = x + _A_ref(_layernorm(x, axis=-1), A_wqkv, A_wo)
    h2 = h + _B_ref(_layernorm(h, axis=-1), B_w1, B_b1, B_w2, B_b2)
    return h2
```

```cpp
#include <cuda_runtime.h>
#include <cuda_bf16.h>
#include <cuda.h>
#include <stdint.h>

namespace {

constexpr int S_ = 2048, D_ = 640, H_ = 32, F_ = 1728;

__device__ __align__(1024) uint8_t g_q[H_ * 256 * 384];
__device__ __align__(1024) uint8_t g_kv[H_ * 16 * 12288];
__device__ __align__(16) float g_kmax2[H_ * 128];
__device__ __align__(1024) uint8_t g_o[S_ * D_ * 2];
__device__ float2 g_hstat[S_];
__device__ __align__(1024) uint8_t g_hn[S_ * D_ * 2];
__device__ __align__(1024) uint8_t g_u[D_ * F_ * 2];
__device__ __align__(16) uint2 g_rowstat[S_];
__device__ __align__(16) uint2 g_cs[3 * D_ / 2];
__device__ __align__(16) uint2 g_hpart[S_ * 8];
__device__ __align__(32) unsigned int g_cnt[8];
__device__ __align__(1024) uint8_t g_wo[D_ * D_ * 2];

__device__ __forceinline__ uint32_t smem_u32(const void* p) { return (uint32_t)__cvta_generic_to_shared(p); }
__device__ __forceinline__ void mbar_init(uint32_t a, int c) { asm volatile("mbarrier.init.shared::cta.b64 [%0], %1;" :: "r"(a), "r"(c)); }
__device__ __forceinline__ void mbar_expect(uint32_t a, uint32_t b) { asm volatile("mbarrier.arrive.expect_tx.shared::cta.b64 _, [%0], %1;" :: "r"(a), "r"(b) : "memory"); }
__device__ __forceinline__ void mbar_arrive(uint32_t a) { asm volatile("mbarrier.arrive.shared::cta.b64 _, [%0];" :: "r"(a) : "memory"); }
__device__ __forceinline__ bool mbar_try(uint32_t a, uint32_t p) {
  uint32_t ok;
  asm volatile("{\n.reg .pred P;\nmbarrier.try_wait.parity.shared::cta.b64 P, [%1], %2;\nselp.b32 %0, 1, 0, P;\n}" : "=r"(ok) : "r"(a), "r"(p) : "memory");
  return ok;
}
__device__ __forceinline__ void mbar_wait(uint32_t a, uint32_t p) {
  if (mbar_try(a, p)) return;
  #pragma unroll 1
  for (int i = 0; i < 4000000; i++) if (mbar_try(a, p)) return;
  __trap();
}
__device__ __forceinline__ void fence_mbar_init() { asm volatile("fence.mbarrier_init.release.cluster;" ::: "memory"); }
__device__ __forceinline__ void bulk_g2s(uint32_t dst, const void* src, uint32_t bytes, uint32_t bar) {
  asm volatile("cp.async.bulk.shared::cluster.global.mbarrier::complete_tx::bytes [%0], [%1], %2, [%3];"
    :: "r"(dst), "l"(src), "r"(bytes), "r"(bar) : "memory");
}
__device__ __forceinline__ void bulk_g2s_mc(uint32_t dst, const void* src, uint32_t bytes, uint32_t bar, uint16_t mask) {
  asm volatile("cp.async.bulk.shared::cluster.global.mbarrier::complete_tx::bytes.multicast::cluster [%0], [%1], %2, [%3], %4;"
    :: "r"(dst), "l"(src), "r"(bytes), "r"(bar), "h"(mask) : "memory");
}
__device__ __forceinline__ void tma2d(uint32_t dst, const CUtensorMap* tm, int c0, int c1, uint32_t bar) {
  asm volatile("cp.async.bulk.tensor.2d.shared::cluster.global.mbarrier::complete_tx::bytes [%0], [%1, {%3, %4}], [%2];"
    :: "r"(dst), "l"(tm), "r"(bar), "r"(c0), "r"(c1) : "memory");
}
__device__ __forceinline__ void mbar_arrive_cta(uint32_t a, uint32_t cta) {
  asm volatile("{\n.reg .b32 r;\nmapa.shared::cluster.u32 r, %0, %1;\nmbarrier.arrive.shared::cluster.b64 _, [r];\n}" :: "r"(a), "r"(cta) : "memory");
}
__device__ __forceinline__ void spin_until(const unsigned int* p, unsigned int target) {
  #pragma unroll 1
  for (int i = 0; i < 4000000; i++) {
    unsigned int v; asm volatile("ld.acquire.gpu.global.u32 %0, [%1];" : "=r"(v) : "l"(p) : "memory");
    if (v >= target) return;
    __nanosleep(20);
  }
  __trap();
}
__device__ __forceinline__ void cluster_wait() { asm volatile("barrier.cluster.wait.acquire.aligned;" ::: "memory"); }
__device__ __forceinline__ void prefetch_tmap(const CUtensorMap* tm) { asm volatile("prefetch.tensormap [%0];" :: "l"(tm) : "memory"); }
__device__ __forceinline__ void pdl_wait() { asm volatile("griddepcontrol.wait;" ::: "memory"); }
__device__ __forceinline__ void pdl_launch() { asm volatile("griddepcontrol.launch_dependents;" ::: "memory"); }
__device__ __forceinline__ uint64_t mk64(uint32_t lo, uint32_t hi) { return ((uint64_t)hi << 32) | lo; }
__device__ __forceinline__ void wg_fence() { asm volatile("wgmma.fence.sync.aligned;" ::: "memory"); }
__device__ __forceinline__ void wg_commit() { asm volatile("wgmma.commit_group.sync.aligned;" ::: "memory"); }
template<int N> __device__ __forceinline__ void wg_wait() { asm volatile("wgmma.wait_group.sync.aligned %0;" :: "n"(N) : "memory"); }
__device__ __forceinline__ float ex2f(float x) { float r; asm("ex2.approx.ftz.f32 %0, %1;" : "=f"(r) : "f"(x)); return r; }
__device__ __forceinline__ uint32_t pack_bf16(float lo, float hi) { uint32_t r; asm("cvt.rn.bf16x2.f32 %0, %1, %2;" : "=r"(r) : "f"(hi), "f"(lo)); return r; }
__device__ __forceinline__ uint32_t hfma2bf(uint32_t a, uint32_t b, uint32_t c) { uint32_t r; asm("fma.rn.bf16x2 %0, %1, %2, %3;" : "=r"(r) : "r"(a), "r"(b), "r"(c)); return r; }
__device__ __forceinline__ float bflo(uint32_t v) { return __uint_as_float(v << 16); }
__device__ __forceinline__ float bfhi(uint32_t v) { return __uint_as_float(v & 0xFFFF0000u); }
template<int N> __device__ __forceinline__ void fence_regs(float (&d)[N]) {
  #pragma unroll
  for (int i = 0; i < N; i++) asm volatile("" : "+f"(d[i]) :: "memory");
}
__device__ __forceinline__ void named_bar(int id, int n) { asm volatile("bar.sync %0, %1;" :: "r"(id), "r"(n) : "memory"); }
__device__ __forceinline__ bool named_bar_or(int id, int n, bool v) {
  uint32_t r;
  asm volatile("{\n.reg .pred p, q;\nsetp.ne.u32 p, %3, 0;\nbar.red.or.pred q, %1, %2, p;\nselp.u32 %0, 1, 0, q;\n}" : "=r"(r) : "r"(id), "r"(n), "r"((uint32_t)v) : "memory");
  return r;
}

template<int TB> __device__ __forceinline__ void wgmma_m64n24k16_rs1(float (&d)[12], uint32_t a0, uint32_t a1, uint32_t a2, uint32_t a3, uint64_t descB) {
  asm volatile("wgmma.mma_async.sync.aligned.m64n24k16.f32.bf16.bf16 {%0, %1, %2, %3, %4, %5, %6, %7, %8, %9, %10, %11}, {%12, %13, %14, %15}, %16, 1, 1, 1, %17;\n"
    : "+f"(d[0]), "+f"(d[1]), "+f"(d[2]), "+f"(d[3]), "+f"(d[4]), "+f"(d[5]), "+f"(d[6]), "+f"(d[7]), "+f"(d[8]), "+f"(d[9]), "+f"(d[10]), "+f"(d[11])
    : "r"(a0), "r"(a1), "r"(a2), "r"(a3), "l"(descB), "n"(TB));
}

template<int TB> __device__ __forceinline__ void wgmma_m64n64k16_rs0(float (&d)[32], uint32_t a0, uint32_t a1, uint32_t a2, uint32_t a3, uint64_t descB) {
  asm volatile("wgmma.mma_async.sync.aligned.m64n64k16.f32.bf16.bf16 {%0, %1, %2, %3, %4, %5, %6, %7, %8, %9, %10, %11, %12, %13, %14, %15, %16, %17, %18, %19, %20, %21, %22, %23, %24, %25, %26, %27, %28, %29, %30, %31}, {%32, %33, %34, %35}, %36, 0, 1, 1, %37;\n"
    : "=f"(d[0]), "=f"(d[1]), "=f"(d[2]), "=f"(d[3]), "=f"(d[4]), "=f"(d[5]), "=f"(d[6]), "=f"(d[7]), "=f"(d[8]), "=f"(d[9]), "=f"(d[10]), "=f"(d[11]), "=f"(d[12]), "=f"(d[13]), "=f"(d[14]), "=f"(d[15]), "=f"(d[16]), "=f"(d[17]), "=f"(d[18]), "=f"(d[19]), "=f"(d[20]), "=f"(d[21]), "=f"(d[22]), "=f"(d[23]), "=f"(d[24]), "=f"(d[25]), "=f"(d[26]), "=f"(d[27]), "=f"(d[28]), "=f"(d[29]), "=f"(d[30]), "=f"(d[31])
    : "r"(a0), "r"(a1), "r"(a2), "r"(a3), "l"(descB), "n"(TB));
}

template<int TB> __device__ __forceinline__ void wgmma_m64n64k16_rs1(float (&d)[32], uint32_t a0, uint32_t a1, uint32_t a2, uint32_t a3, uint64_t descB) {
  asm volatile("wgmma.mma_async.sync.aligned.m64n64k16.f32.bf16.bf16 {%0, %1, %2, %3, %4, %5, %6, %7, %8, %9, %10, %11, %12, %13, %14, %15, %16, %17, %18, %19, %20, %21, %22, %23, %24, %25, %26, %27, %28, %29, %30, %31}, {%32, %33, %34, %35}, %36, 1, 1, 1, %37;\n"
    : "+f"(d[0]), "+f"(d[1]), "+f"(d[2]), "+f"(d[3]), "+f"(d[4]), "+f"(d[5]), "+f"(d[6]), "+f"(d[7]), "+f"(d[8]), "+f"(d[9]), "+f"(d[10]), "+f"(d[11]), "+f"(d[12]), "+f"(d[13]), "+f"(d[14]), "+f"(d[15]), "+f"(d[16]), "+f"(d[17]), "+f"(d[18]), "+f"(d[19]), "+f"(d[20]), "+f"(d[21]), "+f"(d[22]), "+f"(d[23]), "+f"(d[24]), "+f"(d[25]), "+f"(d[26]), "+f"(d[27]), "+f"(d[28]), "+f"(d[29]), "+f"(d[30]), "+f"(d[31])
    : "r"(a0), "r"(a1), "r"(a2), "r"(a3), "l"(descB), "n"(TB));
}

template<int TB> __device__ __forceinline__ void wgmma_m64n128k16_rs0(float (&d)[64], uint32_t a0, uint32_t a1, uint32_t a2, uint32_t a3, uint64_t descB) {
  asm volatile("wgmma.mma_async.sync.aligned.m64n128k16.f32.bf16.bf16 {%0, %1, %2, %3, %4, %5, %6, %7, %8, %9, %10, %11, %12, %13, %14, %15, %16, %17, %18, %19, %20, %21, %22, %23, %24, %25, %26, %27, %28, %29, %30, %31, %32, %33, %34, %35, %36, %37, %38, %39, %40, %41, %42, %43, %44, %45, %46, %47, %48, %49, %50, %51, %52, %53, %54, %55, %56, %57, %58, %59, %60, %61, %62, %63}, {%64, %65, %66, %67}, %68, 0, 1, 1, %69;\n"
    : "=f"(d[0]), "=f"(d[1]), "=f"(d[2]), "=f"(d[3]), "=f"(d[4]), "=f"(d[5]), "=f"(d[6]), "=f"(d[7]), "=f"(d[8]), "=f"(d[9]), "=f"(d[10]), "=f"(d[11]), "=f"(d[12]), "=f"(d[13]), "=f"(d[14]), "=f"(d[15]), "=f"(d[16]), "=f"(d[17]), "=f"(d[18]), "=f"(d[19]), "=f"(d[20]), "=f"(d[21]), "=f"(d[22]), "=f"(d[23]), "=f"(d[24]), "=f"(d[25]), "=f"(d[26]), "=f"(d[27]), "=f"(d[28]), "=f"(d[29]), "=f"(d[30]), "=f"(d[31]), "=f"(d[32]), "=f"(d[33]), "=f"(d[34]), "=f"(d[35]), "=f"(d[36]), "=f"(d[37]), "=f"(d[38]), "=f"(d[39]), "=f"(d[40]), "=f"(d[41]), "=f"(d[42]), "=f"(d[43]), "=f"(d[44]), "=f"(d[45]), "=f"(d[46]), "=f"(d[47]), "=f"(d[48]), "=f"(d[49]), "=f"(d[50]), "=f"(d[51]), "=f"(d[52]), "=f"(d[53]), "=f"(d[54]), "=f"(d[55]), "=f"(d[56]), "=f"(d[57]), "=f"(d[58]), "=f"(d[59]), "=f"(d[60]), "=f"(d[61]), "=f"(d[62]), "=f"(d[63])
    : "r"(a0), "r"(a1), "r"(a2), "r"(a3), "l"(descB), "n"(TB));
}

template<int TB> __device__ __forceinline__ void wgmma_m64n128k16_rs1(float (&d)[64], uint32_t a0, uint32_t a1, uint32_t a2, uint32_t a3, uint64_t descB) {
  asm volatile("wgmma.mma_async.sync.aligned.m64n128k16.f32.bf16.bf16 {%0, %1, %2, %3, %4, %5, %6, %7, %8, %9, %10, %11, %12, %13, %14, %15, %16, %17, %18, %19, %20, %21, %22, %23, %24, %25, %26, %27, %28, %29, %30, %31, %32, %33, %34, %35, %36, %37, %38, %39, %40, %41, %42, %43, %44, %45, %46, %47, %48, %49, %50, %51, %52, %53, %54, %55, %56, %57, %58, %59, %60, %61, %62, %63}, {%64, %65, %66, %67}, %68, 1, 1, 1, %69;\n"
    : "+f"(d[0]), "+f"(d[1]), "+f"(d[2]), "+f"(d[3]), "+f"(d[4]), "+f"(d[5]), "+f"(d[6]), "+f"(d[7]), "+f"(d[8]), "+f"(d[9]), "+f"(d[10]), "+f"(d[11]), "+f"(d[12]), "+f"(d[13]), "+f"(d[14]), "+f"(d[15]), "+f"(d[16]), "+f"(d[17]), "+f"(d[18]), "+f"(d[19]), "+f"(d[20]), "+f"(d[21]), "+f"(d[22]), "+f"(d[23]), "+f"(d[24]), "+f"(d[25]), "+f"(d[26]), "+f"(d[27]), "+f"(d[28]), "+f"(d[29]), "+f"(d[30]), "+f"(d[31]), "+f"(d[32]), "+f"(d[33]), "+f"(d[34]), "+f"(d[35]), "+f"(d[36]), "+f"(d[37]), "+f"(d[38]), "+f"(d[39]), "+f"(d[40]), "+f"(d[41]), "+f"(d[42]), "+f"(d[43]), "+f"(d[44]), "+f"(d[45]), "+f"(d[46]), "+f"(d[47]), "+f"(d[48]), "+f"(d[49]), "+f"(d[50]), "+f"(d[51]), "+f"(d[52]), "+f"(d[53]), "+f"(d[54]), "+f"(d[55]), "+f"(d[56]), "+f"(d[57]), "+f"(d[58]), "+f"(d[59]), "+f"(d[60]), "+f"(d[61]), "+f"(d[62]), "+f"(d[63])
    : "r"(a0), "r"(a1), "r"(a2), "r"(a3), "l"(descB), "n"(TB));
}

template<int TA, int TB> __device__ __forceinline__ void wgmma_m64n240k16_ss1(float (&d)[120], uint64_t descA, uint64_t descB) {
  asm volatile("wgmma.mma_async.sync.aligned.m64n240k16.f32.bf16.bf16 {%0, %1, %2, %3, %4, %5, %6, %7, %8, %9, %10, %11, %12, %13, %14, %15, %16, %17, %18, %19, %20, %21, %22, %23, %24, %25, %26, %27, %28, %29, %30, %31, %32, %33, %34, %35, %36, %37, %38, %39, %40, %41, %42, %43, %44, %45, %46, %47, %48, %49, %50, %51, %52, %53, %54, %55, %56, %57, %58, %59, %60, %61, %62, %63, %64, %65, %66, %67, %68, %69, %70, %71, %72, %73, %74, %75, %76, %77, %78, %79, %80, %81, %82, %83, %84, %85, %86, %87, %88, %89, %90, %91, %92, %93, %94, %95, %96, %97, %98, %99, %100, %101, %102, %103, %104, %105, %106, %107, %108, %109, %110, %111, %112, %113, %114, %115, %116, %117, %118, %119}, %120, %121, 1, 1, 1, %122, %123;\n"
    : "+f"(d[0]), "+f"(d[1]), "+f"(d[2]), "+f"(d[3]), "+f"(d[4]), "+f"(d[5]), "+f"(d[6]), "+f"(d[7]), "+f"(d[8]), "+f"(d[9]), "+f"(d[10]), "+f"(d[11]), "+f"(d[12]), "+f"(d[13]), "+f"(d[14]), "+f"(d[15]), "+f"(d[16]), "+f"(d[17]), "+f"(d[18]), "+f"(d[19]), "+f"(d[20]), "+f"(d[21]), "+f"(d[22]), "+f"(d[23]), "+f"(d[24]), "+f"(d[25]), "+f"(d[26]), "+f"(d[27]), "+f"(d[28]), "+f"(d[29]), "+f"(d[30]), "+f"(d[31]), "+f"(d[32]), "+f"(d[33]), "+f"(d[34]), "+f"(d[35]), "+f"(d[36]), "+f"(d[37]), "+f"(d[38]), "+f"(d[39]), "+f"(d[40]), "+f"(d[41]), "+f"(d[42]), "+f"(d[43]), "+f"(d[44]), "+f"(d[45]), "+f"(d[46]), "+f"(d[47]), "+f"(d[48]), "+f"(d[49]), "+f"(d[50]), "+f"(d[51]), "+f"(d[52]), "+f"(d[53]), "+f"(d[54]), "+f"(d[55]), "+f"(d[56]), "+f"(d[57]), "+f"(d[58]), "+f"(d[59]), "+f"(d[60]), "+f"(d[61]), "+f"(d[62]), "+f"(d[63]), "+f"(d[64]), "+f"(d[65]), "+f"(d[66]), "+f"(d[67]), "+f"(d[68]), "+f"(d[69]), "+f"(d[70]), "+f"(d[71]), "+f"(d[72]), "+f"(d[73]), "+f"(d[74]), "+f"(d[75]), "+f"(d[76]), "+f"(d[77]), "+f"(d[78]), "+f"(d[79]), "+f"(d[80]), "+f"(d[81]), "+f"(d[82]), "+f"(d[83]), "+f"(d[84]), "+f"(d[85]), "+f"(d[86]), "+f"(d[87]), "+f"(d[88]), "+f"(d[89]), "+f"(d[90]), "+f"(d[91]), "+f"(d[92]), "+f"(d[93]), "+f"(d[94]), "+f"(d[95]), "+f"(d[96]), "+f"(d[97]), "+f"(d[98]), "+f"(d[99]), "+f"(d[100]), "+f"(d[101]), "+f"(d[102]), "+f"(d[103]), "+f"(d[104]), "+f"(d[105]), "+f"(d[106]), "+f"(d[107]), "+f"(d[108]), "+f"(d[109]), "+f"(d[110]), "+f"(d[111]), "+f"(d[112]), "+f"(d[113]), "+f"(d[114]), "+f"(d[115]), "+f"(d[116]), "+f"(d[117]), "+f"(d[118]), "+f"(d[119])
    : "l"(descA), "l"(descB), "n"(TA), "n"(TB));
}

template<int TA, int TB> __device__ __forceinline__ void wgmma_m64n80k16_ss1(float (&d)[40], uint64_t descA, uint64_t descB) {
  asm volatile("wgmma.mma_async.sync.aligned.m64n80k16.f32.bf16.bf16 {%0, %1, %2, %3, %4, %5, %6, %7, %8, %9, %10, %11, %12, %13, %14, %15, %16, %17, %18, %19, %20, %21, %22, %23, %24, %25, %26, %27, %28, %29, %30, %31, %32, %33, %34, %35, %36, %37, %38, %39}, %40, %41, 1, 1, 1, %42, %43;\n"
    : "+f"(d[0]), "+f"(d[1]), "+f"(d[2]), "+f"(d[3]), "+f"(d[4]), "+f"(d[5]), "+f"(d[6]), "+f"(d[7]), "+f"(d[8]), "+f"(d[9]), "+f"(d[10]), "+f"(d[11]), "+f"(d[12]), "+f"(d[13]), "+f"(d[14]), "+f"(d[15]), "+f"(d[16]), "+f"(d[17]), "+f"(d[18]), "+f"(d[19]), "+f"(d[20]), "+f"(d[21]), "+f"(d[22]), "+f"(d[23]), "+f"(d[24]), "+f"(d[25]), "+f"(d[26]), "+f"(d[27]), "+f"(d[28]), "+f"(d[29]), "+f"(d[30]), "+f"(d[31]), "+f"(d[32]), "+f"(d[33]), "+f"(d[34]), "+f"(d[35]), "+f"(d[36]), "+f"(d[37]), "+f"(d[38]), "+f"(d[39])
    : "l"(descA), "l"(descB), "n"(TA), "n"(TB));
}

template<int N, int TA, int TB> __device__ __forceinline__ void wgmma_ss(float (&d)[N / 2], uint64_t a, uint64_t b) {
  if constexpr (N == 240) wgmma_m64n240k16_ss1<TA, TB>(d, a, b);
  else wgmma_m64n80k16_ss1<TA, TB>(d, a, b);
}

struct Maps { CUtensorMap a, b; };

#define CS_DELAY 300
#define POLL0 300
#define POLL1 150
#define NMM 5
constexpr int NM_MUFU = NMM;
constexpr float QSCALE = 0.22360679774997896f * 1.4426950408889634f;

template<int EPI, int NWG, int BN, int KB, int STAGES, int PW, int PRE>
struct Gemm {
  static constexpr bool WA = EPI >= 4;
  static constexpr int BM = NWG * 64;
  static constexpr int NBOX = (BN + 63) / 64;
  static constexpr int A_BYTES = BM * 128;
  static constexpr int B_BYTES = WA ? BN * 128 : NBOX * 8192;
  static constexpr int STAGE = A_BYTES + B_BYTES;
  static constexpr int C_BYTES = EPI == 1 ? 16 * D_ * 2 : 0;
  static constexpr int SMEM = STAGE * STAGES + C_BYTES + 1024;
  static constexpr int THREADS = NWG * 128 + 32 * (EPI == 1 ? 4 : PW);
};

__device__ __forceinline__ float gelu_tanh(float x) {
  float t = x * (0.7978845608028654f + 0.035677408136300125f * x * x);
  float th; asm("tanh.approx.f32 %0, %1;" : "=f"(th) : "f"(t));
  const float hx = 0.5f * x;
  return fmaf(hx, th, hx);
}
__device__ __forceinline__ void put2(uint2* p, float a, float b) {
  asm volatile("st.relaxed.gpu.global.v2.b32 [%0], {%1, %2};" :: "l"(p), "r"(~__float_as_uint(a)), "r"(~__float_as_uint(b)) : "memory");
}
__device__ __forceinline__ void gather16(const void* src, void* dst, int n16, int lane) {
  const bool two = lane + 32 < n16;
  const uint4* sa = reinterpret_cast<const uint4*>(src) + lane;
  uint4 a, b = make_uint4(1, 1, 1, 1);
  #pragma unroll 1
  for (int i = 0; ; i++) {
    asm volatile("ld.relaxed.gpu.global.v4.b32 {%0,%1,%2,%3}, [%4];" : "=r"(a.x), "=r"(a.y), "=r"(a.z), "=r"(a.w) : "l"(sa) : "memory");
    if (two) asm volatile("ld.relaxed.gpu.global.v4.b32 {%0,%1,%2,%3}, [%4];" : "=r"(b.x), "=r"(b.y), "=r"(b.z), "=r"(b.w) : "l"(sa + 32) : "memory");
    if (__all_sync(~0u, a.x && a.y && a.z && a.w && b.x && b.y && b.z && b.w)) break;
    if (i > 2000000) __trap();
    __nanosleep(100);
  }
  reinterpret_cast<uint4*>(dst)[lane] = make_uint4(~a.x, ~a.y, ~a.z, ~a.w);
  if (two) reinterpret_cast<uint4*>(dst)[lane + 32] = make_uint4(~b.x, ~b.y, ~b.z, ~b.w);
}
__device__ __forceinline__ void stg32(void* p, uint32_t v) { *reinterpret_cast<uint32_t*>(p) = v; }

template<int EPI, int NWG, int BN, int KB, int STAGES, int PW, int PRE>
__global__ void __launch_bounds__(NWG * 128 + 32 * (EPI == 1 ? 4 : PW), 1)
gemm_kernel(const __grid_constant__ Maps tm, const __nv_bfloat16* __restrict__ p0, const __nv_bfloat16* p1, const __nv_bfloat16* __restrict__ p2) {
  using G = Gemm<EPI, NWG, BN, KB, STAGES, PW, PRE>;
  constexpr bool WA = G::WA;
  extern __shared__ uint8_t smem_raw[];
  __shared__ __align__(8) uint64_t bars[2 * STAGES + 1];
  __shared__ __align__(16) float2 s_stat[EPI == 1 ? 128 : 1];
  __shared__ __align__(16) float s_cs[EPI == 1 ? BN : 1];
  __shared__ float2 s_part[EPI == 1 ? 24 : 1];
  const uint32_t sbase = (smem_u32(smem_raw) + 1023) & ~1023u, cbase = sbase + G::STAGE * STAGES;
  const uint32_t fullb = smem_u32(bars), emptyb = fullb + 8 * STAGES, resb = fullb + 16 * STAGES;
  const int tid = threadIdx.x, lane = tid & 31;
  const int wid = __shfl_sync(~0u, tid >> 5, 0), wg = wid >> 2, warp = wid & 3;
  int bx = blockIdx.x, by = blockIdx.y;
  if (EPI == 1) {
    const int id = blockIdx.y * 8 + blockIdx.x, c = id >> 4, r = id & 15;
    bx = (c & 1) * 4 + (r >> 2); by = (c >> 1) * 4 + (r & 3);
  }
  const int m0 = by * G::BM, n0 = bx * BN;
  auto load_a = [&](int s, int kb) {
    const uint32_t a = sbase + s * G::STAGE, bar = fullb + 8 * s;
    if (WA) { for (int i = 0; i < NWG; i++) tma2d(a + i * 8192, &tm.a, m0 + i * 64, kb * 64, bar); }
    else tma2d(a, &tm.a, kb * 64, m0, bar);
  };
  auto load_b = [&](int s, int kb) {
    const uint32_t b = sbase + s * G::STAGE + G::A_BYTES, bar = fullb + 8 * s;
    if (WA) bulk_g2s(b, (EPI == 4 ? g_hn : g_u) + (kb * 8 + bx) * 10240, 10240, bar);
    else { for (int i = 0; i < G::NBOX; i++) tma2d(b + i * 8192, &tm.b, n0 + i * 64, kb * 64, bar); }
  };
  if (tid == NWG * 128) {
    prefetch_tmap(&tm.a);
    if (!WA) prefetch_tmap(&tm.b);
    for (int i = 0; i < STAGES; i++) { mbar_init(fullb + 8 * i, 1); mbar_init(emptyb + 8 * i, NWG); }
    mbar_init(resb, 1);
    fence_mbar_init();
    if (EPI == 1) { for (int i = 0; i < 2; i++) { mbar_expect(fullb + 8 * i, G::STAGE); load_a(i, i); load_b(i, i); } }
  }
  if (EPI == 1 && tid < 64) {
    reinterpret_cast<uint4*>(g_hpart)[(by * 8 + bx) * 64 + tid] = make_uint4(0, 0, 0, 0);
    if (by * 8 + bx == 0 && tid < 8) g_cnt[tid] = 0;
  }
  __syncthreads();
  pdl_launch();
  if (wg == NWG) {
    if (warp < PW) {
      if (lane == 0) {
        #pragma unroll 1
        for (int s = warp; s < PRE; s += PW) {
          mbar_expect(fullb + 8 * s, G::STAGE);
          if (WA) load_a(s, s); else load_b(s, s);
        }
        if (EPI != 1) pdl_wait();
        #pragma unroll 1
        for (int kb = warp + (EPI == 1 ? 2 : 0); kb < KB; kb += PW) {
          const int it = kb / STAGES, s = kb - it * STAGES;
          if (it > 0) mbar_wait(emptyb + 8 * s, (it - 1) & 1);
          if (kb >= PRE) mbar_expect(fullb + 8 * s, G::STAGE);
          if (WA) { load_b(s, kb); if (kb >= PRE) load_a(s, kb); }
          else { load_a(s, kb); if (kb >= PRE) load_b(s, kb); }
          if (EPI == 1 && kb == 3) { mbar_expect(resb, G::C_BYTES); bulk_g2s(cbase, p0 + (size_t)(m0 + bx * 16) * D_, G::C_BYTES, resb); }
        }
      }
      __syncwarp();
    }
    if constexpr (EPI == 1) {
      if (warp >= 1) {
        __nanosleep(CS_DELAY);
        float cs[8];
        #pragma unroll
        for (int i = 0; i < 8; i++) cs[i] = 0.f;
        const __nv_bfloat16* wp = p1 + (size_t)((warp - 1) * 16 + (lane >> 1)) * (3 * D_) + n0 + min(by, 14) * 16 + (lane & 1) * 8;
        uint4 w[14];
        #pragma unroll
        for (int i = 0; i < 14; i++) {
          w[i] = make_uint4(0, 0, 0, 0);
          if (i < 13 || warp == 1) w[i] = __ldg(reinterpret_cast<const uint4*>(wp + (size_t)i * (48 * 3 * D_)));
        }
        #pragma unroll
        for (int i = 0; i < 14; i++) {
          cs[0] += bflo(w[i].x); cs[1] += bfhi(w[i].x); cs[2] += bflo(w[i].y); cs[3] += bfhi(w[i].y);
          cs[4] += bflo(w[i].z); cs[5] += bfhi(w[i].z); cs[6] += bflo(w[i].w); cs[7] += bfhi(w[i].w);
        }
        #pragma unroll
        for (int i = 0; i < 4; i++) { const bool up = lane & 16; const float t = __shfl_xor_sync(~0u, up ? cs[i] : cs[i + 4], 16); cs[i] = (up ? cs[i + 4] : cs[i]) + t; }
        #pragma unroll
        for (int i = 0; i < 2; i++) { const bool up = lane & 8; const float t = __shfl_xor_sync(~0u, up ? cs[i] : cs[i + 2], 8); cs[i] = (up ? cs[i + 2] : cs[i]) + t; }
        #pragma unroll
        for (int o = 2; o <= 4; o <<= 1) { cs[0] += __shfl_xor_sync(~0u, cs[0], o); cs[1] += __shfl_xor_sync(~0u, cs[1], o); }
        if (!(lane & 6)) s_part[(warp - 1) * 8 + (lane & 1) * 4 + (lane >> 3)] = make_float2(cs[0], cs[1]);
        __syncwarp();
        if (warp < 3) asm volatile("bar.arrive 3, 96;" ::: "memory");
      }
      if (warp == 3) {
        named_bar(3, 96);
        if (by < 15 && lane < 8)
          put2(&g_cs[(n0 + by * 16) / 2 + lane], s_part[lane].x + s_part[8 + lane].x + s_part[16 + lane].x, s_part[lane].y + s_part[8 + lane].y + s_part[16 + lane].y);
        {
          uint4 t[13];
          const int p0i = (by * 8 + bx) * 400 + lane;
          #pragma unroll
          for (int i = 0; i < 13; i++) if (lane + 32 * i < 400) t[i] = __ldg(reinterpret_cast<const uint4*>(p2) + p0i + 32 * i);
          #pragma unroll
          for (int i = 0; i < 13; i++) if (lane + 32 * i < 400) {
            const int p = p0i + 32 * i, k = p / 80, c = p - k * 80, nt = c / 10;
            *reinterpret_cast<uint4*>(g_wo + nt * 102400 + (k >> 3) * 1280 + (c - nt * 10) * 128 + (k & 7) * 16) = t[i];
          }
        }
        gather16(&g_cs[n0 / 2], s_cs, BN / 4, lane);
      } else if (warp >= 1) {
        mbar_wait(resb, 0);
        const uint32_t ra = cbase + ((warp - 1) * 8 + (lane >> 2)) * (D_ * 2) + (((lane & 3) + (lane & 4)) << 4);
        uint4 u[20];
        #pragma unroll
        for (int i = 0; i < 20; i++)
          asm volatile("ld.shared.v4.b32 {%0,%1,%2,%3}, [%4];" : "=r"(u[i].x), "=r"(u[i].y), "=r"(u[i].z), "=r"(u[i].w) : "r"((ra ^ ((i & 1) << 6)) + (i >> 1) * 128));
        float sm[4] = {0.f, 0.f, 0.f, 0.f};
        #pragma unroll
        for (int i = 0; i < 20; i++) {
          sm[0] += bflo(u[i].x) + bfhi(u[i].x); sm[1] += bflo(u[i].y) + bfhi(u[i].y);
          sm[2] += bflo(u[i].z) + bfhi(u[i].z); sm[3] += bflo(u[i].w) + bfhi(u[i].w);
        }
        float mu = (sm[0] + sm[1]) + (sm[2] + sm[3]);
        mu += __shfl_xor_sync(~0u, mu, 1); mu += __shfl_xor_sync(~0u, mu, 2);
        mu *= 1.f / D_;
        float qv[4] = {0.f, 0.f, 0.f, 0.f};
        #pragma unroll
        for (int i = 0; i < 20; i++) {
          float d;
          d = bflo(u[i].x) - mu; qv[0] = fmaf(d, d, qv[0]); d = bfhi(u[i].x) - mu; qv[1] = fmaf(d, d, qv[1]);
          d = bflo(u[i].y) - mu; qv[2] = fmaf(d, d, qv[2]); d = bfhi(u[i].y) - mu; qv[3] = fmaf(d, d, qv[3]);
          d = bflo(u[i].z) - mu; qv[0] = fmaf(d, d, qv[0]); d = bfhi(u[i].z) - mu; qv[1] = fmaf(d, d, qv[1]);
          d = bflo(u[i].w) - mu; qv[2] = fmaf(d, d, qv[2]); d = bfhi(u[i].w) - mu; qv[3] = fmaf(d, d, qv[3]);
        }
        float var = (qv[0] + qv[1]) + (qv[2] + qv[3]);
        var += __shfl_xor_sync(~0u, var, 1); var += __shfl_xor_sync(~0u, var, 2);
        if (!(lane & 3)) put2(&g_rowstat[m0 + bx * 16 + (warp - 1) * 8 + (lane >> 2)], mu, rsqrtf(var * (1.f / D_) + 1e-5f));
        gather16(&g_rowstat[m0 + (warp - 1) * 64], &s_stat[(warp - 1) * 64], 32, lane);
      }
      __syncwarp();
      if (warp) { asm volatile("bar.arrive 1, 224;" ::: "memory"); asm volatile("bar.arrive 2, 224;" ::: "memory"); }
    }
    return;
  }
  const int g = lane >> 2, q = lane & 3;
  const int r0 = wg * 64 + warp * 16 + g;
  const int toff = warp * 2560 + lane * 4;
  uint32_t bv[EPI == 5 ? BN / 4 : 1];
  float2 hs0 = make_float2(0.f, 0.f), hs1 = hs0;
  float b0 = 0.f, b1 = 0.f;
  if (WA && m0 + wg * 64 < (EPI == 4 ? F_ : S_)) { b0 = __bfloat162float(p0[m0 + r0]); b1 = __bfloat162float(p0[m0 + r0 + 8]); }
  float acc[BN / 2];
  #pragma unroll
  for (int i = 0; i < BN / 2; i++) acc[i] = 0.f;
  fence_regs(acc);
  {
    constexpr uint32_t hiS = (1024 >> 4) | (1u << 30);
    constexpr uint32_t hiN = 128 >> 4;
    constexpr uint32_t hiA = hiS, hiB = WA ? hiN : hiS;
    constexpr uint32_t lboA = WA ? (8192 >> 4) : 1, lboB = WA ? (1280 >> 4) : (8192 >> 4);
    constexpr int stepA = EPI == 1 ? 2 : 128, stepB = WA ? 160 : 128;
    constexpr int LAG = 1;
    const uint64_t da0 = mk64((((sbase + wg * 8192) & 0x3FFFF) >> 4) | (lboA << 16), hiA);
    const uint64_t db0 = mk64((((sbase + G::A_BYTES) & 0x3FFFF) >> 4) | (lboB << 16), hiB);
    int s = 0, ph = 0, ps = STAGES - LAG;
    #pragma unroll 1
    for (int kb = 0; kb < KB; kb++) {
      mbar_wait(fullb + 8 * s, ph);
      const uint64_t da = da0 + s * (G::STAGE >> 4), db = db0 + s * (G::STAGE >> 4);
      wg_fence();
      #pragma unroll
      for (int k = 0; k < 4; k++) wgmma_ss<BN, WA, true>(acc, da + k * stepA, db + k * stepB);
      wg_commit();
      if (kb >= LAG && kb - LAG + STAGES < KB) {
        wg_wait<LAG>();
        if ((tid & 127) == 0) mbar_arrive(emptyb + 8 * ps);
      }
      if (++ps == STAGES) ps = 0;
      if (++s == STAGES) { s = 0; ph ^= 1; }
    }
    if constexpr (EPI == 5) {
      hs0 = __ldcg(&g_hstat[m0 + r0]); hs1 = __ldcg(&g_hstat[m0 + r0 + 8]);
      const uint8_t* hp = g_hn + ((by * 2 + wg) * 8 + bx) * 10240 + toff;
      #pragma unroll
      for (int j = 0; j < BN / 8; j++) {
        bv[2 * j] = __ldcg(reinterpret_cast<const uint32_t*>(hp + j * 128));
        bv[2 * j + 1] = __ldcg(reinterpret_cast<const uint32_t*>(hp + j * 128 + 1280));
      }
    }
    wg_wait<0>();
    fence_regs(acc);
  }
  if constexpr (EPI == 1) {
    named_bar(1 + wg, 224);
    const float2 st0 = s_stat[r0], st1 = s_stat[r0 + 8];
    const bool mf0 = ((warp * 2) & 7) < NM_MUFU, mf1 = ((warp * 2 + 1) & 7) < NM_MUFU;
    const uint32_t ek0 = (q & 1) ? (mf0 ? 0x3F803BAAu : 0x3F800000u) : (mf0 ? 0x40263F80u : 0x43C03F80u);
    const uint32_t ek1 = (q & 1) ? (mf1 ? 0x3F803BAAu : 0x3F800000u) : (mf1 ? 0x40263F80u : 0x43C03F80u);
    const uint32_t ev = (q & 1) ? 0u : 0x00003F80u;
    float nrm[BN / 10];
    #pragma unroll
    for (int hp = 0; hp < BN / 40; hp++) {
      const int gh = bx * 12 + 2 * hp, which = gh >> 5, head = gh & 31;
      const float sc = which == 0 ? QSCALE : 1.f, sc0 = st0.y * sc, sc1 = st1.y * sc;
      uint32_t v[10];
      float a[20];
      #pragma unroll
      for (int j = 0; j < 5; j++) {
        const float2 cs = *reinterpret_cast<const float2*>(&s_cs[hp * 40 + j * 8 + 2 * q]);
        const int ai = (hp * 5 + j) * 4;
        a[4 * j] = fmaf(-st0.x, cs.x, acc[ai]) * sc0; a[4 * j + 1] = fmaf(-st0.x, cs.y, acc[ai + 1]) * sc0;
        a[4 * j + 2] = fmaf(-st1.x, cs.x, acc[ai + 2]) * sc1; a[4 * j + 3] = fmaf(-st1.x, cs.y, acc[ai + 3]) * sc1;
        v[2 * j] = pack_bf16(a[4 * j], a[4 * j + 1]); v[2 * j + 1] = pack_bf16(a[4 * j + 2], a[4 * j + 3]);
      }
      const uint32_t e0 = which == 1 ? ek0 : (which == 2 ? ev : 0u), e1 = which == 1 ? ek1 : (which == 2 ? ev : 0u);
      const uint32_t x0 = q < 2 ? v[4] : e0, x1 = q < 2 ? v[5] : e1, y0 = q < 2 ? e0 : v[4], y1 = q < 2 ? e1 : v[5];
      if (which == 1) {
        uint8_t* d = g_kv + (head * 16 + by) * 12288 + wid * 256 + lane * 4;
        stg32(d, v[0]); stg32(d + 128, v[1]); stg32(d + 2048, v[2]); stg32(d + 2176, v[3]); stg32(d + 4096, x0); stg32(d + 4224, x1);
        d += 16 * 12288;
        stg32(d, v[6]); stg32(d + 128, v[7]); stg32(d + 2048, v[8]); stg32(d + 2176, v[9]); stg32(d + 4096, y0); stg32(d + 4224, y1);
        const float m0a = a[8] * a[8] + a[9] * a[9], m1a = a[10] * a[10] + a[11] * a[11];
        nrm[4 * hp] = a[0] * a[0] + a[1] * a[1] + a[4] * a[4] + a[5] * a[5] + (q < 2 ? m0a : 0.f);
        nrm[4 * hp + 1] = a[2] * a[2] + a[3] * a[3] + a[6] * a[6] + a[7] * a[7] + (q < 2 ? m1a : 0.f);
        nrm[4 * hp + 2] = a[12] * a[12] + a[13] * a[13] + a[16] * a[16] + a[17] * a[17] + (q < 2 ? 0.f : m0a);
        nrm[4 * hp + 3] = a[14] * a[14] + a[15] * a[15] + a[18] * a[18] + a[19] * a[19] + (q < 2 ? 0.f : m1a);
      } else {
        uint8_t* d = (which == 0 ? g_q + head * (256 * 384) + by * 6144 : g_kv + (head * 16 + by) * 12288 + 6144) + wid * 768 + lane * 4;
        stg32(d, v[0]); stg32(d + 384, v[1]); stg32(d + 128, v[2]); stg32(d + 512, v[3]); stg32(d + 256, x0); stg32(d + 640, x1);
        d += which == 0 ? 256 * 384 : 16 * 12288;
        stg32(d, v[6]); stg32(d + 384, v[7]); stg32(d + 128, v[8]); stg32(d + 512, v[9]); stg32(d + 256, y0); stg32(d + 640, y1);
        nrm[4 * hp] = nrm[4 * hp + 1] = nrm[4 * hp + 2] = nrm[4 * hp + 3] = 0.f;
      }
    }
    if (bx >= 2 && bx <= 5) {
      #pragma unroll
      for (int o = 1; o < 4; o <<= 1)
        #pragma unroll
        for (int i = 0; i < BN / 10; i++) nrm[i] += __shfl_xor_sync(~0u, nrm[i], o);
      int mine = 0;
      #pragma unroll
      for (int i = 0; i < BN / 20; i++) {
        const int m = __reduce_max_sync(~0u, max(__float_as_int(nrm[2 * i]) & 0x7FFFFFFF, __float_as_int(nrm[2 * i + 1]) & 0x7FFFFFFF));
        if (lane == i) mine = m;
      }
      const int gh = bx * 12 + lane;
      if (lane < 12 && (gh >> 5) == 1) g_kmax2[(gh & 31) * 128 + by * 8 + wid] = __int_as_float(mine);
    }
  } else if constexpr (EPI == 4) {
    if (m0 + wg * 64 < F_) {
      uint8_t* d = g_u + ((by * 2 + wg) * 8 + bx) * 10240 + toff;
      #pragma unroll
      for (int j = 0; j < BN / 8; j++) {
        stg32(d + j * 128, pack_bf16(gelu_tanh(acc[4 * j] + b0), gelu_tanh(acc[4 * j + 1] + b0)));
        stg32(d + j * 128 + 1280, pack_bf16(gelu_tanh(acc[4 * j + 2] + b1), gelu_tanh(acc[4 * j + 3] + b1)));
      }
    }
  } else {
    uint8_t* op = reinterpret_cast<uint8_t*>(const_cast<__nv_bfloat16*>(p1)) + (size_t)(m0 + r0) * (D_ * 2) + n0 * 2 + (q & 1) * 16 + (q >> 1) * 8;
    #pragma unroll
    for (int j = 0; j < BN / 8; j += 2) {
      uint32_t x[4];
      #pragma unroll
      for (int i = 0; i < 4; i++) {
        const float b = (i & 1) ? b1 + hs1.x : b0 + hs0.x, sg = (i & 1) ? hs1.y : hs0.y;
        x[i] = pack_bf16(fmaf(bflo(bv[2 * j + i]), sg, acc[4 * j + 2 * i] + b), fmaf(bfhi(bv[2 * j + i]), sg, acc[4 * j + 2 * i + 1] + b));
      }
      #pragma unroll
      for (int hr = 0; hr < 2; hr++) {
        const uint32_t t = __shfl_xor_sync(~0u, (q & 1) ? x[hr] : x[2 + hr], 1);
        *reinterpret_cast<uint2*>(op + hr * 8 * D_ * 2 + j * 16) = (q & 1) ? make_uint2(t, x[2 + hr]) : make_uint2(x[hr], t);
      }
    }
  }
}

__device__ __forceinline__ uint32_t exp2_pair(float t0, float t1, uint32_t kmone) {
  const uint32_t s = __byte_perm(__float_as_uint(t0), __float_as_uint(t1), 0x6521);
  uint32_t m; asm("lop3.b32 %0, %1, 0x007F007F, %2, 0xEA;" : "=r"(m) : "r"(s), "r"(kmone));
  return hfma2bf(m, m, 0x40034003u) + s - m;
}

constexpr int ATT_SMEM = 16 * 12288 + 24576 + 1024;

__device__ __forceinline__ void attn_store(const float (&o)[12], int row, int head, int lane) {
  const int q = lane & 3, odd = head & 1;
  const int lsrc = (lane & ~3) | (odd ? 0 : 2);
  const float l0 = __shfl_sync(~0u, o[8], lsrc), l1 = __shfl_sync(~0u, o[10], lsrc);
  const float r0 = __fdividef(1.f, l0), r1 = __fdividef(1.f, l1);
  uint8_t* op = g_o + (row >> 6) * 81920 + ((head >> 1) * 5 + odd * 3) * 1024 + ((row >> 3) & 7) * 128 + lane * 4;
  *(uint32_t*)(op) = pack_bf16(o[0] * r0, o[1] * r0);
  *(uint32_t*)(op + 128) = pack_bf16(o[2] * r1, o[3] * r1);
  *(uint32_t*)(op + 1024) = pack_bf16(o[4] * r0, o[5] * r0);
  *(uint32_t*)(op + 1152) = pack_bf16(o[6] * r1, o[7] * r1);
  if ((q >> 1) == odd) {
    op += odd ? -1024 : 2048;
    *(uint32_t*)(op) = pack_bf16(o[8] * r0, o[9] * r0);
    *(uint32_t*)(op + 128) = pack_bf16(o[10] * r1, o[11] * r1);
  }
}
__device__ __forceinline__ uint32_t lds32(uint32_t a) { uint32_t v; asm volatile("ld.shared.b32 %0, [%1];" : "=r"(v) : "r"(a) : "memory"); return v; }

__device__ __forceinline__ void red_release(unsigned int* p) { asm volatile("red.release.gpu.global.add.u32 [%0], 1;" :: "l"(p) : "memory"); }

__device__ __forceinline__ void attn_slow(uint32_t sbase, uint32_t qs, int head, int row0, bool store) {
  const int lane = threadIdx.x & 31;
  constexpr uint32_t dhi = 128 >> 4;
  const uint64_t DK0 = mk64(((sbase & 0x3FFFF) >> 4) | ((2048 >> 4) << 16), dhi), DK1 = mk64(((sbase & 0x3FFFF) + 4096) >> 4, dhi);
  const uint64_t DV0 = mk64((((sbase & 0x3FFFF) + 6144) >> 4) | ((384 >> 4) << 16), dhi);
  const uint32_t qa0 = lds32(qs), qa1 = lds32(qs + 384), qa2 = lds32(qs + 128), qa3 = lds32(qs + 512);
  const uint32_t qb0 = lds32(qs + 256), qb1 = lds32(qs + 640);
  float o[12], s[32]; uint32_t p[16];
  #pragma unroll
  for (int i = 0; i < 12; i++) o[i] = 0.f;
  float m0 = -INFINITY, m1 = -INFINITY;
  #pragma unroll 1
  for (int j = 0; j < 32; j++) {
    const uint32_t off = (j >> 1) * 768;
    wg_fence();
    wgmma_m64n64k16_rs0<0>(s, qa0, qa1, qa2, qa3, DK0 + off + (j & 1) * 64);
    wgmma_m64n64k16_rs1<0>(s, qb0, qb1, 0u, 0u, DK1 + off + (j & 1) * 64);
    wg_commit();
    wg_wait<0>();
    fence_regs(s);
    float x0 = m0, x1 = m1;
    #pragma unroll
    for (int i = 0; i < 8; i++) { x0 = fmaxf(x0, fmaxf(s[4 * i], s[4 * i + 1])); x1 = fmaxf(x1, fmaxf(s[4 * i + 2], s[4 * i + 3])); }
    x0 = fmaxf(x0, __shfl_xor_sync(~0u, x0, 1)); x0 = fmaxf(x0, __shfl_xor_sync(~0u, x0, 2));
    x1 = fmaxf(x1, __shfl_xor_sync(~0u, x1, 1)); x1 = fmaxf(x1, __shfl_xor_sync(~0u, x1, 2));
    const float c0 = ex2f(m0 - x0), c1 = ex2f(m1 - x1);
    m0 = x0; m1 = x1;
    #pragma unroll
    for (int i = 0; i < 3; i++) { o[4 * i] *= c0; o[4 * i + 1] *= c0; o[4 * i + 2] *= c1; o[4 * i + 3] *= c1; }
    #pragma unroll
    for (int i = 0; i < 8; i++) {
      p[2 * i] = pack_bf16(ex2f(s[4 * i] - m0), ex2f(s[4 * i + 1] - m0));
      p[2 * i + 1] = pack_bf16(ex2f(s[4 * i + 2] - m1), ex2f(s[4 * i + 3] - m1));
    }
    fence_regs(o);
    wg_fence();
    #pragma unroll
    for (int kk = 0; kk < 4; kk++)
      wgmma_m64n24k16_rs1<1>(o, p[4 * kk], p[4 * kk + 1], p[4 * kk + 2], p[4 * kk + 3], DV0 + off + (j & 1) * 192 + kk * 48);
    wg_commit();
    wg_wait<0>();
    fence_regs(o);
  }
  if (store) attn_store(o, row0, head, lane);
}

__global__ void __launch_bounds__(512, 1) attn_kernel(const __nv_bfloat16* __restrict__ x, const uint8_t* __restrict__ w1, const uint8_t* __restrict__ w2) {
  extern __shared__ uint8_t smem_raw[];
  __shared__ __align__(8) uint64_t bars[35];
  __shared__ volatile int s_early;
  __shared__ volatile int s_redo;
  const int head = blockIdx.x >> 2, rb = blockIdx.x & 3;
  const uint32_t sbase = (smem_u32(smem_raw) + 1023) & ~1023u, bbase = smem_u32(bars), qbase = sbase + 16 * 12288;
  const uint32_t fb = bbase + 144, fa0 = fb + 8, fa1 = fb + 48, eb = fb + 88, stb = fb + 112, deadb = fb + 120;
  const int tid = threadIdx.x, lane = tid & 31, g = lane >> 2, q = lane & 3;
  const int wid = __shfl_sync(~0u, tid >> 5, 0), wg = wid >> 2, warp = wid & 3;
  if (tid == 0) {
    #pragma unroll
    for (int i = 0; i < 18; i++) mbar_init(bbase + 8 * i, 1);
    #pragma unroll
    for (int i = 0; i < 18; i++) mbar_expect(bbase + 8 * i, i < 4 || i >= 16 ? 12288 : (i & 1 ? 0 : 24576));
    fence_mbar_init();
  } else if (tid == 32) {
    s_redo = 0;
    #pragma unroll
    for (int i = 18; i < 35; i++) mbar_init(bbase + 8 * i, i < 29 ? 1 : (i < 32 ? 2 : 16));
    #pragma unroll
    for (int i = 18; i < 29; i++) mbar_expect(bbase + 8 * i, i == 18 ? 102400 : 16384);
    fence_mbar_init();
  }
  __syncwarp();
  asm volatile("barrier.cluster.arrive.relaxed.aligned;\nbarrier.cluster.wait.aligned;" ::: "memory");
  pdl_launch();
  pdl_wait();
  const uint8_t* kvsrc = g_kv + (size_t)head * (16 * 12288);
  const uint8_t* qsrc = g_q + (size_t)head * (256 * 384) + rb * 24576;
  const int4 kmi = *reinterpret_cast<const int4*>(&g_kmax2[head * 128 + lane * 4]);
  const int hf = (rb & 1) * 6144;
  if ((tid & 127) == 0) {
    if (wg == 3) bulk_g2s(qbase, qsrc, 12288, bbase + 128);
    bulk_g2s_mc(sbase + wg * 12288 + hf, kvsrc + wg * 12288 + hf, 6144, bbase + 8 * wg, 3);
  }
  {
    const int i = tid < 12 ? blockIdx.x * 12 + tid : S_;
    if (i < S_ / 2) reinterpret_cast<uint4*>(g_rowstat)[i] = make_uint4(0, 0, 0, 0);
    else if (i < S_ / 2 + 3 * D_ / 4) reinterpret_cast<uint4*>(g_cs)[i - S_ / 2] = make_uint4(0, 0, 0, 0);
  }
  const float km2 = __int_as_float(__reduce_max_sync(~0u, max(max(kmi.x, kmi.y), max(kmi.z, kmi.w))));
  constexpr uint32_t dhi = 128 >> 4;
  const uint64_t DK0 = mk64(((sbase & 0x3FFFF) >> 4) | ((2048 >> 4) << 16), dhi);
  const uint64_t DK1 = mk64(((sbase & 0x3FFFF) + 4096) >> 4, dhi);
  const uint64_t DV0 = mk64((((sbase & 0x3FFFF) + 6144) >> 4) | ((384 >> 4) << 16), dhi);
  const int eq = q - ((head & 1) ? 0 : 2);
  const int bx = blockIdx.x & 7, t = blockIdx.x >> 3, mt0 = (t >> 2) * 8 + (t & 3);
  int redo = 0;
  #pragma unroll 1
  for (int pass = 0; pass < 2; pass++) {
    const int lrow = pass * 256 + wg * 64 + warp * 16;
    mbar_wait(bbase + 128 + 8 * pass, 0);
    const uint32_t qs = qbase + (lrow >> 3) * 384 + g * 16 + q * 4;
    const uint32_t qa0 = lds32(qs), qa1 = lds32(qs + 384), qa2 = lds32(qs + 128), qa3 = lds32(qs + 512);
    uint32_t qb0 = lds32(qs + 256), qb1 = lds32(qs + 640);
    const uint32_t zs = qbase + 256 + ((head & 1) ? 0 : 8);
    const uint32_t qz0 = lds32(zs), qz1 = lds32(zs + 4), kmone = lds32(zs + 16) + 0xBF80BF80u;
    auto sq = [](uint32_t v) { return bflo(v) * bflo(v) + bfhi(v) * bfhi(v); };
    float n0 = sq(qa0) + sq(qa2) + sq(qb0), n1 = sq(qa1) + sq(qa3) + sq(qb1);
    n0 += __shfl_xor_sync(~0u, n0, 1); n1 += __shfl_xor_sync(~0u, n1, 1);
    n0 += __shfl_xor_sync(~0u, n0, 2); n1 += __shfl_xor_sync(~0u, n1, 2);
    float b0, b1;
    asm("sqrt.approx.f32 %0, %1;" : "=f"(b0) : "f"(n0 * km2)); asm("sqrt.approx.f32 %0, %1;" : "=f"(b1) : "f"(n1 * km2));
    b0 *= 1.01f; b1 *= 1.01f;
    bool bad = !(b0 <= 48.f && b1 <= 48.f);
    float o[12], s[64];
    uint32_t p0[16], p1[16];
    if (eq == 0) { qb0 = pack_bf16(-b0, 1.f); qb1 = pack_bf16(-b1, 0.f); }
    if (eq == 1) { qb0 = 0x00003F80u; qb1 = 0x43C00000u; }
    #pragma unroll
    for (int i = 0; i < 12; i++) o[i] = 0.f;
    fence_regs(o);
    auto smpv = [&](uint32_t (&p)[16], int h, uint64_t d) {
      #pragma unroll
      for (int i = 0; i < 8; i++) {
        const int b = 32 * h + 4 * i;
        if (i < NM_MUFU) p[2 * i] = pack_bf16(ex2f(s[b]), ex2f(s[b + 1]));
        else p[2 * i] = exp2_pair(s[b], s[b + 1], kmone);
        p[2 * i + 1] = exp2_pair(s[b + 2], s[b + 3], kmone);
      }
      wg_fence();
      #pragma unroll
      for (int kk = 0; kk < 4; kk++)
        wgmma_m64n24k16_rs1<1>(o, p[4 * kk], p[4 * kk + 1], p[4 * kk + 2], p[4 * kk + 3], d + kk * 48);
      wg_commit();
    };
    int ev = pass ? (wid == 8 ? 3 : 9) : (wid == 12 ? 6 : (wid == 4 ? 0 : -1));
    uint32_t bar_addr = bbase;
    uint64_t D0 = DK0, D1 = DK1, DV = DV0;
    #pragma unroll 1
    for (int it = 0; it < 16; it++) {
      mbar_wait(bar_addr, 0);
      bar_addr += 8;
      wg_fence();
      wgmma_m64n128k16_rs0<0>(s, qa0, qa1, qa2, qa3, D0);
      wgmma_m64n128k16_rs1<0>(s, qb0, qb1, qz0, qz1, D1);
      wg_commit();
      wg_wait<0>();
      fence_regs(s);
      smpv(p0, 0, DV);
      smpv(p1, 1, DV + 192);
      wg_wait<1>();
      D0 += 768; D1 += 768; DV += 768;
      if (it == ev) {
        if (it == 0) {
          const int i = 4 + 4 * lane + 2 * (rb & 1);
          asm volatile("{\n.reg .pred p;\nsetp.lt.u32 p, %4, 3;\n@p cp.async.bulk.shared::cluster.global.mbarrier::complete_tx::bytes.multicast::cluster [%0], [%1], 24576, [%2], %3;\n}"
            :: "r"(sbase + i * 12288), "l"(kvsrc + i * 12288), "r"(bbase + 8 * i), "h"((uint16_t)3), "r"(lane) : "memory");
          asm volatile("{\n.reg .pred p;\nsetp.eq.u32 p, %3, 0;\n@p cp.async.bulk.shared::cluster.global.mbarrier::complete_tx::bytes [%0], [%1], 12288, [%2];\n}"
            :: "r"(qbase + 12288), "l"(qsrc + 12288), "r"(bbase + 136), "r"(lane) : "memory");
        } else if (it == 3) {
          mbar_wait(stb, 0);
          asm volatile("{\n.reg .pred p;\nsetp.eq.u32 p, %1, 0;\n@p red.release.gpu.global.add.u32 [%0], 1;\n}" :: "l"(&g_cnt[rb]), "r"(lane | s_redo) : "memory");
          ev = 9;
        } else if (it == 9 || it == 13) {
          asm volatile("{\n.reg .pred p;\nsetp.eq.u32 p, %1, 0;\n@p mbarrier.arrive.shared::cta.b64 _, [%0];\n}" :: "r"(deadb + 2 * (it - 9)), "r"(lane) : "memory");
          ev = it == 9 ? (wid == 0 ? 11 : 13) : (wid == 4 ? 14 : -1);
        } else if (it == 14) {
          mbar_wait(deadb + 8, 0);
          uint32_t cnt;
          asm volatile("ld.acquire.gpu.global.u32 %0, [%1];" : "=r"(cnt) : "l"(&g_cnt[blockIdx.x >> 5]) : "memory");
          asm volatile("fence.proxy.async.global;" ::: "memory");
          s_early = cnt >= 32u;
          asm volatile("{\n.reg .pred p;\nsetp.lt.u32 p, %3, 3;\n@p cp.async.bulk.shared::cluster.global.mbarrier::complete_tx::bytes [%0], [%1], 16384, [%2];\n}"
            :: "r"(sbase + 102400 + lane * 16384), "l"(g_o + mt0 * 81920 + lane * 16384), "r"(fa0 + 8 * lane), "r"(cnt >= 32u ? lane : 3) : "memory");
        } else if (it == 11) {
          mbar_wait(deadb, 0);
          asm volatile("{\n.reg .pred p;\nsetp.eq.u32 p, %3, 0;\n@p cp.async.bulk.shared::cluster.global.mbarrier::complete_tx::bytes [%0], [%1], 102400, [%2];\n}"
            :: "r"(sbase), "l"(g_wo + bx * 102400), "r"(fb), "r"(lane) : "memory");
          ev = 13;
        } else {
          asm volatile("{\n.reg .pred p;\nsetp.lt.u32 p, %1, 2;\n@p cp.async.bulk.prefetch.L2.global [%0], 55296;\n}"
            :: "l"((lane ? w2 : w1) + blockIdx.x * 55296), "r"(lane) : "memory");
        }
      }
    }
    wg_wait<0>();
    fence_regs(o);
    bad = bad || (eq == 0 && !(o[8] >= 1e-18f && o[8] <= 1e30f && o[10] >= 1e-18f && o[10] <= 1e30f));
    attn_store(o, rb * 512 + lrow, head, lane);
    redo |= (__any_sync(~0u, bad) ? 1 : 0) << pass;
    if (redo & 1) s_redo = 1;
    asm volatile("{\n.reg .pred p;\nsetp.eq.u32 p, %1, 0;\n@p mbarrier.arrive.shared::cta.b64 _, [%0];\n}" :: "r"(stb), "r"(lane | pass) : "memory");
  }
  const int mt = mt0 + 4 * (wg & 1), row = mt * 64 + warp * 16 + g;
  uint32_t bv[20];
  if (wg < 2) {
    #pragma unroll
    for (int j = 0; j < 10; j++) {
      bv[2 * j] = __ldg(reinterpret_cast<const uint32_t*>(x + (size_t)row * D_ + bx * 80 + 8 * j + 2 * q));
      bv[2 * j + 1] = __ldg(reinterpret_cast<const uint32_t*>(x + (size_t)(row + 8) * D_ + bx * 80 + 8 * j + 2 * q));
    }
  }
  uint32_t bph = 0, aph = 0;
  const int any_redo = __shfl_sync(~0u, __syncthreads_or(redo), 0);
  if (any_redo) {
    mbar_wait(fb, 0);
    if (__shfl_sync(~0u, s_early, 0)) { mbar_wait(fa0, 0); mbar_wait(fa0 + 8, 0); mbar_wait(fa0 + 16, 0); aph = 1; }
    __syncthreads();
    if (tid == 0) {
      mbar_expect(bbase, 13 * 12288); bulk_g2s(sbase, kvsrc, 13 * 12288, bbase);
      if (s_early) { mbar_expect(fa0, 16384); mbar_expect(fa0 + 8, 16384); mbar_expect(fa0 + 16, 16384); s_early = 0; }
    }
    mbar_wait(bbase, 1);
    #pragma unroll 1
    for (int pass = 0; pass < 2; pass++) {
      const int lrow = pass * 256 + wg * 64 + warp * 16;
      if (__shfl_sync(~0u, (int)named_bar_or(1 + wg, 128, (redo >> pass) & 1), 0))
        attn_slow(sbase, qbase + (lrow >> 3) * 384 + g * 16 + q * 4, head, rb * 512 + lrow, (redo >> pass) & 1);
    }
    __syncthreads();
    if (tid == 0) {
      mbar_expect(fb, 102400); bulk_g2s(sbase, g_wo + bx * 102400, 102400, fb);
      if (s_redo) red_release(&g_cnt[rb]);
    }
    __syncwarp();
    bph = 1;
  }
  asm volatile("barrier.cluster.arrive.relaxed.aligned;" ::: "memory");
  const uint32_t abase = sbase + 102400;
  if (wg >= 2) {
    if (tid == 384) red_release(&g_cnt[4 + rb]);
    if (tid == 256) {
      const int c0 = s_early ? 3 : 0;
      if (!c0) { spin_until(&g_cnt[t >> 2], 32u); asm volatile("fence.proxy.async.global;" ::: "memory"); }
      #pragma unroll 1
      for (int c = c0; c < 5; c++) bulk_g2s(abase + c * 16384, g_o + mt0 * 81920 + c * 16384, 16384, fa0 + 8 * c);
    }
    __syncwarp();
    cluster_wait();
    const int half = (bx & 1) * 8192;
    if (tid == 288) {
      spin_until(&g_cnt[4 + (t >> 2)], 32u);
      asm volatile("fence.proxy.async.global;" ::: "memory");
      #pragma unroll
      for (int c = 0; c < 5; c++) {
        if (c >= 2) mbar_wait(eb + 8 * (c - 2), 0);
        bulk_g2s_mc(abase + (c < 2 ? c + 5 : c - 2) * 16384 + half, g_o + (mt0 + 4) * 81920 + c * 16384 + half, 8192, fa1 + 8 * c, 3);
      }
    }
    return;
  }
  float acc[40];
  #pragma unroll
  for (int i = 0; i < 40; i++) acc[i] = 0.f;
  fence_regs(acc);
  {
    const uint32_t da0 = ((abase & 0x3FFFF) >> 4) | ((1024 >> 4) << 16);
    const uint32_t db0 = ((sbase & 0x3FFFF) >> 4) | ((1280 >> 4) << 16);
    const uint32_t fa = wg ? fa1 : fa0;
    mbar_wait(fb, bph);
    #pragma unroll 1
    for (int c = 0; c < 5; c++) {
      mbar_wait(fa + 8 * c, wg == 0 && c < 3 ? aph : 0);
      const int slot = wg ? (c < 2 ? c + 5 : c - 2) : c;
      const uint32_t da = __shfl_sync(~0u, da0 + slot * 1024, 0), db = __shfl_sync(~0u, db0 + c * 1280, 0);
      wg_fence();
      #pragma unroll
      for (int k = 0; k < 8; k++) wgmma_m64n80k16_ss1<0, 1>(acc, mk64(da + k * 128, dhi), mk64(db + k * 160, dhi));
      wg_commit();
      if (wg == 0 && c >= 1 && c <= 3) {
        wg_wait<1>();
        named_bar(1, 128);
        if (tid < 2) mbar_arrive_cta(eb + 8 * (c - 1), tid);
      }
    }
    wg_wait<0>();
    fence_regs(acc);
  }
  cluster_wait();
  float s0[2] = {0.f, 0.f}, s1[2] = {0.f, 0.f};
  #pragma unroll
  for (int i = 0; i < 20; i++) {
    acc[2 * i] += bflo(bv[i]); acc[2 * i + 1] += bfhi(bv[i]);
    if (i & 1) s1[(i >> 1) & 1] += acc[2 * i] + acc[2 * i + 1]; else s0[(i >> 1) & 1] += acc[2 * i] + acc[2 * i + 1];
  }
  float a0 = s0[0] + s0[1], a1 = s1[0] + s1[1];
  a0 += __shfl_xor_sync(~0u, a0, 1); a1 += __shfl_xor_sync(~0u, a1, 1);
  a0 += __shfl_xor_sync(~0u, a0, 2); a1 += __shfl_xor_sync(~0u, a1, 2);
  a0 *= 1.f / 80; a1 *= 1.f / 80;
  float v[4] = {0.f, 0.f, 0.f, 0.f};
  #pragma unroll
  for (int j = 0; j < 10; j++) {
    float d;
    d = acc[4 * j] - a0; v[0] = fmaf(d, d, v[0]); d = acc[4 * j + 1] - a0; v[1] = fmaf(d, d, v[1]);
    d = acc[4 * j + 2] - a1; v[2] = fmaf(d, d, v[2]); d = acc[4 * j + 3] - a1; v[3] = fmaf(d, d, v[3]);
  }
  float v0 = v[0] + v[1], v1 = v[2] + v[3];
  v0 += __shfl_xor_sync(~0u, v0, 1); v1 += __shfl_xor_sync(~0u, v1, 1);
  v0 += __shfl_xor_sync(~0u, v0, 2); v1 += __shfl_xor_sync(~0u, v1, 2);
  if (q < 2) put2(&g_hpart[(row + 8 * q) * 8 + bx], q ? a1 : a0, q ? v1 : v0);
  const int blk = (mt * 8 + bx) * 10240 + warp * 2560 + lane * 4;
  uint4 pa, pb;
  {
    const uint4* sa = reinterpret_cast<const uint4*>(&g_hpart[row * 8 + 2 * q]);
    #pragma unroll 1
    for (int i = 0; ; i++) {
      if (wg) __nanosleep(i ? POLL1 : POLL0);
      asm volatile("ld.relaxed.gpu.global.v4.b32 {%0,%1,%2,%3}, [%4];" : "=r"(pa.x), "=r"(pa.y), "=r"(pa.z), "=r"(pa.w) : "l"(sa) : "memory");
      asm volatile("ld.relaxed.gpu.global.v4.b32 {%0,%1,%2,%3}, [%4];" : "=r"(pb.x), "=r"(pb.y), "=r"(pb.z), "=r"(pb.w) : "l"(sa + 32) : "memory");
      if (__all_sync(~0u, pa.x && pa.y && pa.z && pa.w && pb.x && pb.y && pb.z && pb.w)) break;
      if (i > 2000000) __trap();
    }
  }
  float mu[2], rs[2];
  #pragma unroll
  for (int hrow = 0; hrow < 2; hrow++) {
    const uint4 p = hrow ? pb : pa;
    const float ma = __uint_as_float(~p.x), mb = __uint_as_float(~p.z);
    float m = ma + mb;
    m += __shfl_xor_sync(~0u, m, 1); m += __shfl_xor_sync(~0u, m, 2);
    m *= 0.125f;
    float m2 = __uint_as_float(~p.y) + __uint_as_float(~p.w) + 80.f * ((ma - m) * (ma - m) + (mb - m) * (mb - m));
    m2 += __shfl_xor_sync(~0u, m2, 1); m2 += __shfl_xor_sync(~0u, m2, 2);
    const float var = m2 * (1.f / D_);
    float r = rsqrtf(var + 1e-5f);
    r *= rsqrtf(var * r * r + 1e-5f);
    mu[hrow] = -m * r; rs[hrow] = r;
    if (bx == 0 && q == 0) g_hstat[row + 8 * hrow] = make_float2(m, 1.f / r);
  }
  #pragma unroll
  for (int j = 0; j < 10; j++) {
    stg32(g_hn + blk + j * 128, pack_bf16(fmaf(acc[4 * j], rs[0], mu[0]), fmaf(acc[4 * j + 1], rs[0], mu[0])));
    stg32(g_hn + blk + j * 128 + 1280, pack_bf16(fmaf(acc[4 * j + 2], rs[1], mu[1]), fmaf(acc[4 * j + 3], rs[1], mu[1])));
  }
}

typedef CUresult (*EncodeFn)(CUtensorMap*, CUtensorMapDataType, cuuint32_t, void*, const cuuint64_t*, const cuuint64_t*,
                             const cuuint32_t*, const cuuint32_t*, CUtensorMapInterleave, CUtensorMapSwizzle,
                             CUtensorMapL2promotion, CUtensorMapFloatOOBfill);

CUtensorMap make_map(EncodeFn enc, const void* base, int inner, int outer, int box_inner, int box_outer, bool swz = true) {
  CUtensorMap m;
  cuuint64_t dims[2] = {(cuuint64_t)inner, (cuuint64_t)outer};
  cuuint64_t strides[1] = {(cuuint64_t)inner * 2};
  cuuint32_t box[2] = {(cuuint32_t)box_inner, (cuuint32_t)box_outer};
  cuuint32_t es[2] = {1, 1};
  enc(&m, CU_TENSOR_MAP_DATA_TYPE_BFLOAT16, 2, const_cast<void*>(base), dims, strides, box, es, CU_TENSOR_MAP_INTERLEAVE_NONE,
      swz ? CU_TENSOR_MAP_SWIZZLE_128B : CU_TENSOR_MAP_SWIZZLE_NONE, CU_TENSOR_MAP_L2_PROMOTION_L2_128B, CU_TENSOR_MAP_FLOAT_OOB_FILL_NONE);
  return m;
}

template<class K, class... Args>
void launch(K kern, dim3 grid, int threads, int smem, bool pdl, dim3 cl, Args... args) {
  cudaLaunchConfig_t cfg = {};
  cfg.gridDim = grid; cfg.blockDim = dim3(threads); cfg.dynamicSmemBytes = smem; cfg.stream = cudaStreamPerThread;
  cudaLaunchAttribute at[2];
  int n = 0;
  if (pdl) { at[n].id = cudaLaunchAttributeProgrammaticStreamSerialization; at[n].val.programmaticStreamSerializationAllowed = 1; n++; }
  if (cl.x * cl.y > 1) { at[n].id = cudaLaunchAttributeClusterDimension; at[n].val.clusterDim.x = cl.x; at[n].val.clusterDim.y = cl.y; at[n].val.clusterDim.z = 1; n++; }
  cfg.attrs = at; cfg.numAttrs = n;
  cudaLaunchKernelEx(&cfg, kern, args...);
}

#define CL4X 4
#define CL4Y 2
#define CL5X 1
#define CL5Y 1
#define PRE4 3
#define PRE5 3
#define P1 1, 2, 240, 10, 4, 1, 0
#define P4 4, 2, 80, 32, 8, 4, PRE4
#define P5 5, 2, 80, 27, 8, 4, PRE5

}

#define USE_PDL 1

extern "C" void kernel_launch(void* const* d_in, const int* in_sizes, int n_in, void* d_out, int out_size) {
  const __nv_bfloat16* x = (const __nv_bfloat16*)d_in[0];
  const __nv_bfloat16* wqkv = (const __nv_bfloat16*)d_in[1];
  const __nv_bfloat16* wo = (const __nv_bfloat16*)d_in[2];
  const __nv_bfloat16* w1 = (const __nv_bfloat16*)d_in[4];
  const __nv_bfloat16* b1 = (const __nv_bfloat16*)d_in[5];
  const __nv_bfloat16* w2 = (const __nv_bfloat16*)d_in[6];
  const __nv_bfloat16* b2 = (const __nv_bfloat16*)d_in[7];
  __nv_bfloat16* out = (__nv_bfloat16*)d_out;

  EncodeFn enc = nullptr;
  cudaDriverEntryPointQueryResult qr;
  cudaGetDriverEntryPoint("cuTensorMapEncodeTiled", (void**)&enc, cudaEnableDefault, &qr);
  cudaFuncSetAttribute(gemm_kernel<P1>, cudaFuncAttributeMaxDynamicSharedMemorySize, Gemm<P1>::SMEM);
  cudaFuncSetAttribute(gemm_kernel<P4>, cudaFuncAttributeMaxDynamicSharedMemorySize, Gemm<P4>::SMEM);
  cudaFuncSetAttribute(gemm_kernel<P5>, cudaFuncAttributeMaxDynamicSharedMemorySize, Gemm<P5>::SMEM);
  cudaFuncSetAttribute(attn_kernel, cudaFuncAttributeMaxDynamicSharedMemorySize, ATT_SMEM);
  Maps t1, t4, t5;
  t1.a = make_map(enc, x, D_, S_, 64, 128); t1.b = make_map(enc, wqkv, 3 * D_, D_, 64, 64);
  t4.a = make_map(enc, w1, F_, S_, 64, 64); t4.b = t4.a;
  t5.a = make_map(enc, w2, S_, F_, 64, 64); t5.b = t5.a;

  const bool pdl = USE_PDL;
  const __nv_bfloat16* nul = nullptr;
  launch(gemm_kernel<P1>, dim3(8, 16), Gemm<P1>::THREADS, Gemm<P1>::SMEM, false, dim3(1, 1), t1, x, wqkv, wo);
  launch(attn_kernel, dim3(128), 512, ATT_SMEM, pdl, dim3(2, 1), x, (const uint8_t*)w1, (const uint8_t*)w2);
  launch(gemm_kernel<P4>, dim3(8, 14), Gemm<P4>::THREADS, Gemm<P4>::SMEM, pdl, dim3(CL4X, CL4Y), t4, b1, nul, nul);
  launch(gemm_kernel<P5>, dim3(8, 16), Gemm<P5>::THREADS, Gemm<P5>::SMEM, pdl, dim3(CL5X, CL5Y), t5, b2, (const __nv_bfloat16*)out, nul);
}
```
